```python
import torch

def _softmax(x, axis=-1):
    return torch.softmax(x, dim=axis)
def _gelu(x):
    return torch.nn.functional.gelu(x, approximate="tanh")
def _silu(x):
    return torch.nn.functional.silu(x)
def _sigmoid(x):
    return torch.sigmoid(x)
def _layernorm(x, axis=-1, eps=1e-5):
    m = x.mean(dim=axis, keepdim=True)
    v = x.var(dim=axis, keepdim=True, unbiased=False)
    return (x - m) / torch.sqrt(v + eps)
def _scatter_add(tgt, idx, src, axis=0):
    return tgt.clone().index_add_(axis, idx, src)
def _segment_sum(src, seg, n):
    out = torch.zeros((n,) + src.shape[1:], dtype=src.dtype)
    return out.index_add_(0, seg, src)
def _pad(x, pw):
    flat = tuple(v for pair in reversed(pw) for v in pair)
    return torch.nn.functional.pad(x, flat)

kernel_name = 'parallel_sum__ssm_conv_s5__mixer_token_mlp__prompt'

def setup_inputs():

    _w = (lambda a: (lambda t: t.to(torch.bfloat16) if t.is_floating_point() else t)(torch.as_tensor(a)))
    def _A_setup():
        B, S, D = 1, 2048, 448
        P = D
        Lambda_re = -0.5 * (lambda _x: torch.exp(torch.as_tensor(_x)))((lambda *s: torch.randn(*s, dtype=torch.bfloat16) * 0.1)(P))
        Lambda_im = (lambda *s: torch.randn(*s, dtype=torch.bfloat16) * 0.4)(P) * 1.0
        B_re = (lambda *s: torch.randn(*s, dtype=torch.bfloat16) * 0.2)(P, D) * (D ** -0.5)
        B_im = (lambda *s: torch.randn(*s, dtype=torch.bfloat16) * 0.2)(P, D) * (D ** -0.5)
        C_re = (lambda *s: torch.randn(*s, dtype=torch.bfloat16) * 0.2)(D, P) * (P ** -0.5)
        C_im = (lambda *s: torch.randn(*s, dtype=torch.bfloat16) * 0.2)(D, P) * (P ** -0.5)
        log_dt = (lambda *s: torch.randn(*s, dtype=torch.bfloat16) * 0.1)(P) * 0.3 - 2.0
        Dskip = (lambda *s: torch.randn(*s, dtype=torch.bfloat16) * 0.05)(D)
        return {
            "x": _w((lambda *s: torch.randn(*s, dtype=torch.bfloat16) * 0.05)(B, S, D)),
            "Lambda_re": _w(Lambda_re),
            "Lambda_im": _w(Lambda_im),
            "B_re": _w(B_re),
            "B_im": _w(B_im),
            "C_re": _w(C_re),
            "C_im": _w(C_im),
            "log_dt": _w(log_dt),
            "Dskip": _w(Dskip),
        }
    _A_in = _A_setup()

    def _B_setup():
        B, S, D, F = 1, 2048, 448, 1792
        return {
            "x": _w((lambda *s: torch.randn(*s, dtype=torch.bfloat16) * 0.05)(B, S, D)),
            "w1": _w((lambda *s: torch.randn(*s, dtype=torch.bfloat16) * 0.8)(S, F) * (S ** -0.5)),
            "b1": _w((lambda *s: torch.randn(*s, dtype=torch.bfloat16) * 3.2)(F) * 0.02),
            "w2": _w((lambda *s: torch.randn(*s, dtype=torch.bfloat16) * 0.4)(F, S) * (F ** -0.5)),
            "b2": _w((lambda *s: torch.randn(*s, dtype=torch.bfloat16) * 1.6)(S) * 0.02),
        }
    _B_in = _B_setup()

    return {
        "A_x": _A_in["x"],
        "A_Lambda_re": _A_in["Lambda_re"],
        "A_Lambda_im": _A_in["Lambda_im"],
        "A_B_re": _A_in["B_re"],
        "A_B_im": _A_in["B_im"],
        "A_C_re": _A_in["C_re"],
        "A_C_im": _A_in["C_im"],
        "A_log_dt": _A_in["log_dt"],
        "A_Dskip": _A_in["Dskip"],
        "B_x": _B_in["x"],
        "B_w1": _B_in["w1"],
        "B_b1": _B_in["b1"],
        "B_w2": _B_in["w2"],
        "B_b2": _B_in["b2"],
    }

def reference(A_x, A_Lambda_re, A_Lambda_im, A_B_re, A_B_im, A_C_re, A_C_im, A_log_dt, A_Dskip, B_x, B_w1, B_b1, B_w2, B_b2):
    def _A_ref(x, Lambda_re, Lambda_im, B_re, B_im, C_re, C_im, log_dt, Dskip):
        Bsz, L, H = x.shape
        Lam = Lambda_re + 1j * Lambda_im
        Bmat = B_re + 1j * B_im
        Cmat = C_re + 1j * C_im
        dt = torch.exp(log_dt)
        Lam_bar = torch.exp(dt * Lam)
        B_bar = ((Lam_bar - 1.0) / Lam)[:, None] * Bmat
        Bu = torch.einsum("bld,pd->blp", x + 0j, B_bar)
        h = torch.zeros_like(Bu[:, 0, :])
        hs = []
        for t in range(L):
            h = Lam_bar[None, :] * h + Bu[:, t, :]
            hs.append(h)
        hseq = torch.stack(hs, 1)
        y = 2.0 * torch.einsum("blp,dp->bld", hseq, Cmat).real + x * Dskip[None, None, :]
        return y

    def _B_ref(x, w1, b1, w2, b2):
        B, S, D = x.shape
        h = _layernorm(x, axis=-1)
        u = torch.einsum("bsd,sf->bdf", h, w1) + b1
        u = _gelu(u)
        y = torch.einsum("bdf,fs->bds", u, w2) + b2
        return (lambda x, *d: x.permute(*d))(y, 0, 2, 1)

    x = A_x
    xn = _layernorm(x, axis=-1)
    return x + _A_ref(xn, A_Lambda_re, A_Lambda_im, A_B_re, A_B_im, A_C_re, A_C_im, A_log_dt, A_Dskip) + _B_ref(xn, B_w1, B_b1, B_w2, B_b2)
```

```cpp
#include <cuda_runtime.h>
#include <cuda_bf16.h>
#include <cuda.h>
#include <stdint.h>

namespace {

constexpr int S_ = 2048, D_ = 448, F_ = 1792;
constexpr int NCTA = 112;
constexpr int SLOT = 24576, NSLOT = 8;
constexpr int OFF_STG = NSLOT * SLOT;
constexpr int OFF_LAM = OFF_STG + 32768;
constexpr int OFF_BAR = OFF_LAM + 1024;
constexpr int OFF_STAT = OFF_BAR + 592;
constexpr int OFF_B2 = OFF_STAT + 1088;
constexpr int SMEM_BYTES = OFF_B2 + 256;
static_assert(SMEM_BYTES <= 232448, "smem");

enum { B_FULLA = 0, B_EP = 7, B_FULLB = 8, B_FULLC = 16, B_HREAD = 24, B_XT = 25, B_STAT = 26, B_BDONE = 27, B_H1 = 28, B_GALL = 29, B_LAM = 30,
       B_ECM = 32, B_ECN = 40, B_EBM = 48, B_EBN = 56, B_FULLA2 = 64, B_GOWN = 72, B_LNM = 73 };
constexpr int G1A_AHEAD = 3;
constexpr int HGAP = 240;
constexpr int EWAIT = 400;
constexpr int TAILK = 5;
constexpr int PF_W1 = 8, PF_W2 = 8;
constexpr uint32_t BYTES_B = 8192 + 14336, BYTES_C = 24576;
constexpr int SPIN_LIMIT = 4000000;

enum { C_LN = 0, C_H = 16, C_G = 48, C_C = 76, C_TOTAL = 83 };

struct Maps {
  CUtensorMap bi, x5, nst, w1, hn64, hn48, hld, w2, cld, gld, hst, gst, ost, xt;
};

struct Scratch {
  uint32_t cnt[3072];
  float2 stats[S_ + 1024];
  uint2 E[16 * D_];
  __nv_bfloat16 hn[4 * S_ * 128];
  __nv_bfloat16 hT[896 * S_];
  __nv_bfloat16 cp[D_ * 896];
  __nv_bfloat16 gc[F_ * D_];
};
__device__ __align__(1024) Scratch g_sc;
#define TR(k) do {} while (0)
#define FINE(ch, i, fl) do {} while (0)
#define LT_DECL
#define LT(i, fl) do {} while (0)
#define LTX(i, fl) do {} while (0)
#define LT_DUMP(ch, off) do {} while (0)
#define RT(i) do {} while (0)
#define RT_DUMP(k0) do {} while (0)
#define TPARAM
#define TARG(ch, off)

__device__ __forceinline__ uint32_t smem_u32(const void* p) { return (uint32_t)__cvta_generic_to_shared(p); }
__device__ __forceinline__ void mbar_init(uint32_t bar, uint32_t cnt) { asm volatile("mbarrier.init.shared::cta.b64 [%0], %1;" :: "r"(bar), "r"(cnt) : "memory"); }
__device__ __forceinline__ void mbar_expect_tx(uint32_t bar, uint32_t bytes) { asm volatile("mbarrier.arrive.expect_tx.shared::cta.b64 _, [%0], %1;" :: "r"(bar), "r"(bytes) : "memory"); }
__device__ __forceinline__ void mbar_arrive(uint32_t bar) { asm volatile("mbarrier.arrive.shared::cta.b64 _, [%0];" :: "r"(bar) : "memory"); }
__device__ __forceinline__ bool mbar_test(uint32_t bar, uint32_t parity) {
  uint32_t ok;
  asm volatile("{\n.reg .pred p;\nmbarrier.test_wait.parity.shared::cta.b64 p, [%1], %2;\nselp.u32 %0, 1, 0, p;\n}" : "=r"(ok) : "r"(bar), "r"(parity) : "memory");
  return ok;
}
__device__ __forceinline__ void mbar_wait(uint32_t bar, uint32_t parity) {
  asm volatile("{\n.reg .pred p;\n.reg .b32 n;\nmov.b32 n, %2;\nW_%=:\nmbarrier.try_wait.parity.shared::cta.b64 p, [%0], %1;\n@p bra.uni D_%=;\n"
               "add.s32 n, n, -1;\nsetp.ne.b32 p, n, 0;\n@p bra.uni W_%=;\ntrap;\nD_%=:\n}" :: "r"(bar), "r"(parity), "n"(SPIN_LIMIT) : "memory");
}
__device__ __forceinline__ void mbar_wait_mma(uint32_t bar, uint32_t parity) {
  asm volatile("{\n.reg .pred p;\nW_%=:\nmbarrier.try_wait.parity.shared::cta.b64 p, [%0], %1;\n@!p bra.uni W_%=;\n}" :: "r"(bar), "r"(parity) : "memory");
}
__device__ __forceinline__ uint32_t mapa(uint32_t a, uint32_t cta) { uint32_t r; asm volatile("mapa.shared::cluster.u32 %0, %1, %2;" : "=r"(r) : "r"(a), "r"(cta)); return r; }
__device__ __forceinline__ bool elect_one() { uint32_t p; asm volatile("{\n.reg .pred P;\nelect.sync _|P, 0xffffffff;\nselp.u32 %0, 1, 0, P;\n}" : "=r"(p)); return p; }
__device__ __forceinline__ void tma2(uint32_t dst, const CUtensorMap* m, int c0, int c1, uint32_t bar, uint16_t mask) {
  asm volatile("cp.async.bulk.tensor.2d.shared::cluster.global.mbarrier::complete_tx::bytes.multicast::cluster [%0], [%1, {%3, %4}], [%2], %5;"
               :: "r"(dst), "l"(m), "r"(bar), "r"(c0), "r"(c1), "h"(mask) : "memory");
}
__device__ __forceinline__ void tma3(uint32_t dst, const CUtensorMap* m, int c0, int c1, int c2, uint32_t bar, uint16_t mask) {
  asm volatile("cp.async.bulk.tensor.3d.shared::cluster.global.mbarrier::complete_tx::bytes.multicast::cluster [%0], [%1, {%3, %4, %5}], [%2], %6;"
               :: "r"(dst), "l"(m), "r"(bar), "r"(c0), "r"(c1), "r"(c2), "h"(mask) : "memory");
}
__device__ __forceinline__ void tma4(uint32_t dst, const CUtensorMap* m, int c0, int c3, uint32_t bar, uint16_t mask) {
  asm volatile("cp.async.bulk.tensor.4d.shared::cluster.global.mbarrier::complete_tx::bytes.multicast::cluster [%0], [%1, {%3, %5, %5, %4}], [%2], %6;"
               :: "r"(dst), "l"(m), "r"(bar), "r"(c0), "r"(c3), "r"(0), "h"(mask) : "memory");
}
__device__ __forceinline__ void tma5(uint32_t dst, const CUtensorMap* m, int c0, int c4, uint32_t bar, uint16_t mask) {
  asm volatile("cp.async.bulk.tensor.5d.shared::cluster.global.mbarrier::complete_tx::bytes.multicast::cluster [%0], [%1, {%3, %5, %5, %5, %4}], [%2], %6;"
               :: "r"(dst), "l"(m), "r"(bar), "r"(c0), "r"(c4), "r"(0), "h"(mask) : "memory");
}
__device__ __forceinline__ void tma_st2(const CUtensorMap* m, uint32_t src, int c0, int c1) {
  asm volatile("cp.async.bulk.tensor.2d.global.shared::cta.bulk_group [%0, {%2, %3}], [%1];" :: "l"(m), "r"(src), "r"(c0), "r"(c1) : "memory");
}
__device__ __forceinline__ void tma_st3(const CUtensorMap* m, uint32_t src, int c0, int c1, int c2) {
  asm volatile("cp.async.bulk.tensor.3d.global.shared::cta.bulk_group [%0, {%2, %3, %4}], [%1];" :: "l"(m), "r"(src), "r"(c0), "r"(c1), "r"(c2) : "memory");
}
__device__ __forceinline__ void tma_pf2(const CUtensorMap* m, int c0, int c1) {
  asm volatile("cp.async.bulk.prefetch.tensor.2d.L2.global [%0, {%1, %2}];" :: "l"(m), "r"(c0), "r"(c1) : "memory");
}
__device__ __forceinline__ void tma_pf3(const CUtensorMap* m, int c0, int c1, int c2) {
  asm volatile("cp.async.bulk.prefetch.tensor.3d.L2.global [%0, {%1, %2, %3}];" :: "l"(m), "r"(c0), "r"(c1), "r"(c2) : "memory");
}
__device__ __forceinline__ void bulk_commit() { asm volatile("cp.async.bulk.commit_group;" ::: "memory"); }
__device__ __forceinline__ void bulk_wait0() { asm volatile("cp.async.bulk.wait_group 0;" ::: "memory"); }
__device__ __forceinline__ void bulk_wait_read0() { asm volatile("cp.async.bulk.wait_group.read 0;" ::: "memory"); }
__device__ __forceinline__ void prefetch_l2(const void* p, uint32_t bytes) { asm volatile("cp.async.bulk.prefetch.L2.global [%0], %1;" :: "l"(p), "r"(bytes) : "memory"); }
__device__ __forceinline__ void prefetch_map(const CUtensorMap* m) { asm volatile("prefetch.tensormap [%0];" :: "l"(m) : "memory"); }
__device__ __forceinline__ void fence_async_smem() { asm volatile("fence.proxy.async.shared::cta;" ::: "memory"); }
__device__ __forceinline__ void fence_async_global() { asm volatile("fence.proxy.async.global;" ::: "memory"); }
__device__ __forceinline__ void wg_fence() { asm volatile("wgmma.fence.sync.aligned;" ::: "memory"); }
__device__ __forceinline__ void wg_commit() { asm volatile("wgmma.commit_group.sync.aligned;" ::: "memory"); }
template <int N> __device__ __forceinline__ void wg_wait() { asm volatile("wgmma.wait_group.sync.aligned %0;" :: "n"(N) : "memory"); }
#define named_bar(id, n) asm volatile("bar.sync %0, %1;" :: "n"(id), "n"(n) : "memory")
__device__ __forceinline__ void cluster_arrive_relaxed() { asm volatile("barrier.cluster.arrive.relaxed.aligned;" ::: "memory"); }
__device__ __forceinline__ void cluster_wait() { asm volatile("barrier.cluster.wait.aligned;" ::: "memory"); }
__device__ __forceinline__ void red_release(uint32_t* p) { asm volatile("red.release.gpu.global.add.u32 [%0], 1;" :: "l"(p) : "memory"); }
__device__ __forceinline__ void red_relaxed(uint32_t* p) { asm volatile("red.relaxed.gpu.global.add.u32 [%0], 1;" :: "l"(p) : "memory"); }
__device__ __forceinline__ uint32_t ldg_u16(const void* p) { uint32_t v; asm volatile("ld.global.nc.u16 %0, [%1];" : "=r"(v) : "l"(p)); return v; }
__device__ __forceinline__ uint32_t ld_weak(const uint32_t* p) { uint32_t v; asm volatile("ld.global.cg.u32 %0, [%1];" : "=r"(v) : "l"(p)); return v; }
__device__ __forceinline__ uint32_t ld_acquire(const uint32_t* p) { uint32_t v; asm volatile("ld.acquire.gpu.global.u32 %0, [%1];" : "=r"(v) : "l"(p) : "memory"); return v; }
__device__ __forceinline__ void poll_counters(const uint32_t* cnt, int first, int n, uint32_t target, int lane) {
  const uint32_t* p = cnt + (first + (lane < n ? lane : 0)) * 32;
  int it = 0;
  while (true) {
    uint32_t v = ld_acquire(p);
    if (__all_sync(0xffffffffu, (int)(v - target) >= 0)) break;
    __nanosleep(40);
    if (++it > SPIN_LIMIT) __trap();
  }
}
template <class F>
__device__ __forceinline__ void run_half(int odd, uint32_t ebar, F issue) {
  ebar += 8 * odd;
#pragma unroll 1
  for (int r = 0; r < 4; r++) {
#pragma unroll
    for (int k = 0; k < 4; k++) {
      mbar_wait(ebar + 16 * k, r & 1);
      if (elect_one()) issue(r, k);
    }
  }
}
template <class F>
__device__ __forceinline__ void run_seg(int& n, int step, int end, uint32_t ebar, uint32_t& lt0, uint32_t& lt1, F issue) {
#pragma unroll 1
  for (; n < end; n += step) {
    mbar_wait(ebar + 8 * (n & 7), (n >> 3) & 1);
    LT(n, 0);
    if (elect_one()) issue(n);
  }
}
constexpr uint32_t DESC_HI = (1024u >> 4) | (1u << 30);
__device__ __forceinline__ uint64_t mkdesc(uint32_t lo) { return ((uint64_t)DESC_HI << 32) | lo; }
__host__ __device__ constexpr uint32_t desc_lo(uint32_t addr, uint32_t lbo) { return ((addr & 0x3FFFF) >> 4) | ((lbo >> 4) << 16); }
__device__ __forceinline__ float bf_lo(uint32_t w) { return __uint_as_float(w << 16); }
__device__ __forceinline__ float bf_hi(uint32_t w) { return __uint_as_float(w & 0xffff0000u); }
__device__ __forceinline__ float bfr(float v) { return __bfloat162float(__float2bfloat16_rn(v)); }
__device__ __forceinline__ uint32_t pack_bf(float lo, float hi) { uint32_t r; asm("cvt.rn.bf16x2.f32 %0, %1, %2;" : "=r"(r) : "f"(hi), "f"(lo)); return r; }
__device__ __forceinline__ float4 lds128(uint32_t a) { float4 v; asm volatile("ld.shared.v4.f32 {%0,%1,%2,%3}, [%4];" : "=f"(v.x), "=f"(v.y), "=f"(v.z), "=f"(v.w) : "r"(a)); return v; }
__device__ __forceinline__ float2 lds64(uint32_t a) { float2 v; asm volatile("ld.shared.v2.f32 {%0,%1}, [%2];" : "=f"(v.x), "=f"(v.y) : "r"(a)); return v; }
__device__ __forceinline__ float lds32(uint32_t a) { float v; asm volatile("ld.shared.f32 %0, [%1];" : "=f"(v) : "r"(a)); return v; }
__device__ __forceinline__ uint4 ldg_nc(const void* p) { uint4 v; asm volatile("ld.global.nc.L1::no_allocate.v4.u32 {%0,%1,%2,%3}, [%4];" : "=r"(v.x), "=r"(v.y), "=r"(v.z), "=r"(v.w) : "l"(p)); return v; }
__device__ __forceinline__ float2 cmul(float2 a, float2 b) { return make_float2(a.x * b.x - a.y * b.y, a.x * b.y + a.y * b.x); }
__device__ __forceinline__ float2 csq(float2 a) { return make_float2(fmaf(a.x, a.x, -a.y * a.y), (a.x + a.x) * a.y); }
__device__ __forceinline__ float2 cfma(float2 a, float2 b, float2 c) { return make_float2(fmaf(a.x, b.x, fmaf(-a.y, b.y, c.x)), fmaf(a.x, b.y, fmaf(a.y, b.x, c.y))); }

template <int N> __device__ __forceinline__ void fence_regs(float (&a)[N]) {
#pragma unroll
  for (int i = 0; i < N; i++) asm volatile("" : "+f"(a[i]) :: "memory");
}
__device__ __forceinline__ void fence_c(float2& a) { asm volatile("" : "+f"(a.x), "+f"(a.y) :: "memory"); }
template<int TA, int TB> __device__ __forceinline__ void wgmma_n64(float (&d)[32], uint64_t da, uint64_t db, int sd) {
  asm volatile("{\n.reg .pred p;\nsetp.ne.b32 p, %34, 0;\n"
    "wgmma.mma_async.sync.aligned.m64n64k16.f32.bf16.bf16 {%0, %1, %2, %3, %4, %5, %6, %7, %8, %9, %10, %11, %12, %13, %14, %15, %16, %17, %18, %19, %20, %21, %22, %23, %24, %25, %26, %27, %28, %29, %30, %31}, %32, %33, p, 1, 1, %35, %36;\n}"
    : "+f"(d[0]), "+f"(d[1]), "+f"(d[2]), "+f"(d[3]), "+f"(d[4]), "+f"(d[5]), "+f"(d[6]), "+f"(d[7]), "+f"(d[8]), "+f"(d[9]), "+f"(d[10]), "+f"(d[11]), "+f"(d[12]), "+f"(d[13]), "+f"(d[14]), "+f"(d[15]), "+f"(d[16]), "+f"(d[17]), "+f"(d[18]), "+f"(d[19]), "+f"(d[20]), "+f"(d[21]), "+f"(d[22]), "+f"(d[23]), "+f"(d[24]), "+f"(d[25]), "+f"(d[26]), "+f"(d[27]), "+f"(d[28]), "+f"(d[29]), "+f"(d[30]), "+f"(d[31])
    : "l"(da), "l"(db), "r"(sd), "n"(TA), "n"(TB));
}
template<int TA, int TB> __device__ __forceinline__ void wgmma_n112(float (&d)[56], uint64_t da, uint64_t db, int sd) {
  asm volatile("{\n.reg .pred p;\nsetp.ne.b32 p, %58, 0;\n"
    "wgmma.mma_async.sync.aligned.m64n112k16.f32.bf16.bf16 {%0, %1, %2, %3, %4, %5, %6, %7, %8, %9, %10, %11, %12, %13, %14, %15, %16, %17, %18, %19, %20, %21, %22, %23, %24, %25, %26, %27, %28, %29, %30, %31, %32, %33, %34, %35, %36, %37, %38, %39, %40, %41, %42, %43, %44, %45, %46, %47, %48, %49, %50, %51, %52, %53, %54, %55}, %56, %57, p, 1, 1, %59, %60;\n}"
    : "+f"(d[0]), "+f"(d[1]), "+f"(d[2]), "+f"(d[3]), "+f"(d[4]), "+f"(d[5]), "+f"(d[6]), "+f"(d[7]), "+f"(d[8]), "+f"(d[9]), "+f"(d[10]), "+f"(d[11]), "+f"(d[12]), "+f"(d[13]), "+f"(d[14]), "+f"(d[15]), "+f"(d[16]), "+f"(d[17]), "+f"(d[18]), "+f"(d[19]), "+f"(d[20]), "+f"(d[21]), "+f"(d[22]), "+f"(d[23]), "+f"(d[24]), "+f"(d[25]), "+f"(d[26]), "+f"(d[27]), "+f"(d[28]), "+f"(d[29]), "+f"(d[30]), "+f"(d[31]), "+f"(d[32]), "+f"(d[33]), "+f"(d[34]), "+f"(d[35]), "+f"(d[36]), "+f"(d[37]), "+f"(d[38]), "+f"(d[39]), "+f"(d[40]), "+f"(d[41]), "+f"(d[42]), "+f"(d[43]), "+f"(d[44]), "+f"(d[45]), "+f"(d[46]), "+f"(d[47]), "+f"(d[48]), "+f"(d[49]), "+f"(d[50]), "+f"(d[51]), "+f"(d[52]), "+f"(d[53]), "+f"(d[54]), "+f"(d[55])
    : "l"(da), "l"(db), "r"(sd), "n"(TA), "n"(TB));
}
template<int TA, int TB> __device__ __forceinline__ void wgmma_n128(float (&d)[64], uint64_t da, uint64_t db, int sd) {
  asm volatile("{\n.reg .pred p;\nsetp.ne.b32 p, %66, 0;\n"
    "wgmma.mma_async.sync.aligned.m64n128k16.f32.bf16.bf16 {%0, %1, %2, %3, %4, %5, %6, %7, %8, %9, %10, %11, %12, %13, %14, %15, %16, %17, %18, %19, %20, %21, %22, %23, %24, %25, %26, %27, %28, %29, %30, %31, %32, %33, %34, %35, %36, %37, %38, %39, %40, %41, %42, %43, %44, %45, %46, %47, %48, %49, %50, %51, %52, %53, %54, %55, %56, %57, %58, %59, %60, %61, %62, %63}, %64, %65, p, 1, 1, %67, %68;\n}"
    : "+f"(d[0]), "+f"(d[1]), "+f"(d[2]), "+f"(d[3]), "+f"(d[4]), "+f"(d[5]), "+f"(d[6]), "+f"(d[7]), "+f"(d[8]), "+f"(d[9]), "+f"(d[10]), "+f"(d[11]), "+f"(d[12]), "+f"(d[13]), "+f"(d[14]), "+f"(d[15]), "+f"(d[16]), "+f"(d[17]), "+f"(d[18]), "+f"(d[19]), "+f"(d[20]), "+f"(d[21]), "+f"(d[22]), "+f"(d[23]), "+f"(d[24]), "+f"(d[25]), "+f"(d[26]), "+f"(d[27]), "+f"(d[28]), "+f"(d[29]), "+f"(d[30]), "+f"(d[31]), "+f"(d[32]), "+f"(d[33]), "+f"(d[34]), "+f"(d[35]), "+f"(d[36]), "+f"(d[37]), "+f"(d[38]), "+f"(d[39]), "+f"(d[40]), "+f"(d[41]), "+f"(d[42]), "+f"(d[43]), "+f"(d[44]), "+f"(d[45]), "+f"(d[46]), "+f"(d[47]), "+f"(d[48]), "+f"(d[49]), "+f"(d[50]), "+f"(d[51]), "+f"(d[52]), "+f"(d[53]), "+f"(d[54]), "+f"(d[55]), "+f"(d[56]), "+f"(d[57]), "+f"(d[58]), "+f"(d[59]), "+f"(d[60]), "+f"(d[61]), "+f"(d[62]), "+f"(d[63])
    : "l"(da), "l"(db), "r"(sd), "n"(TA), "n"(TB));
}

__device__ __forceinline__ float rcp_fast(float v) { float r; asm("rcp.approx.f32 %0, %1;" : "=f"(r) : "f"(v)); return r; }
__device__ __forceinline__ uint32_t hsub2(uint32_t a, uint32_t b) { uint32_t r; asm("sub.rn.bf16x2 %0, %1, %2;" : "=r"(r) : "r"(a), "r"(b)); return r; }
__device__ __forceinline__ uint32_t hmul2(uint32_t a, uint32_t b) { uint32_t r; asm("mul.rn.bf16x2 %0, %1, %2;" : "=r"(r) : "r"(a), "r"(b)); return r; }
__device__ __forceinline__ uint32_t hfma2(uint32_t a, uint32_t b, uint32_t c) { uint32_t r; asm("fma.rn.bf16x2 %0, %1, %2, %3;" : "=r"(r) : "r"(a), "r"(b), "r"(c)); return r; }
__device__ __forceinline__ void mma16816(float (&c)[4], uint32_t a0, uint32_t a1, uint32_t a2, uint32_t a3, uint32_t b0, uint32_t b1) {
  asm("mma.sync.aligned.m16n8k16.row.col.f32.bf16.bf16.f32 {%0,%1,%2,%3}, {%4,%5,%6,%7}, {%8,%9}, {%0,%1,%2,%3};"
      : "+f"(c[0]), "+f"(c[1]), "+f"(c[2]), "+f"(c[3]) : "r"(a0), "r"(a1), "r"(a2), "r"(a3), "r"(b0), "r"(b1));
}
__device__ __forceinline__ void mma1688(float (&c)[4], uint32_t a0, uint32_t a1, uint32_t b0) {
  asm("mma.sync.aligned.m16n8k8.row.col.f32.bf16.bf16.f32 {%0,%1,%2,%3}, {%4,%5}, {%6}, {%0,%1,%2,%3};"
      : "+f"(c[0]), "+f"(c[1]), "+f"(c[2]), "+f"(c[3]) : "r"(a0), "r"(a1), "r"(b0));
}
#define SCHED_FENCE(k) do { if (P.zero & (1u << (k))) __trap(); } while (0)
__device__ __forceinline__ void release_slot(bool p, uint32_t bar, uint32_t tx) {
  asm volatile("{\n.reg .pred p;\nsetp.ne.u32 p, %0, 0;\n@p mbarrier.arrive.expect_tx.shared::cluster.b64 _, [%1], %2;\n}" :: "r"((uint32_t)p), "r"(bar), "r"(tx) : "memory");
}

struct Params {
  const __nv_bfloat16 *x, *bre, *bim, *cre, *cim;
  Scratch* sc;
  uint32_t zero, swap;
  const __nv_bfloat16 *b1, *lre, *lim, *logdt, *dskip, *b2;
  uint4 tab[NCTA];
  Maps m;
};
#define LEAD(w, stream, odd) (((w) >> (8 * (stream) + 4 * (odd))) & 15)
enum { S_AM = 0, S_AN = 1, S_BM = 2, S_BN = 3 };
#define GET_EPOCH() mbar_wait(bars + 8 * B_EP, 0); const uint32_t ep = __float_as_uint(lds32(base + OFF_STAT + 256))

__global__ void __launch_bounds__(512, 1)
s5_mixer_kernel(const __grid_constant__ Params P) {
  extern __shared__ __align__(1024) uint8_t smem_raw[];
  if (threadIdx.x == 480) {
    prefetch_l2(reinterpret_cast<const uint8_t*>(P.x) + blockIdx.x * 16384, 16384);
    prefetch_l2(reinterpret_cast<const uint8_t*>(P.bre) + blockIdx.x * 3584, 3584);
    prefetch_l2(reinterpret_cast<const uint8_t*>(P.bim) + blockIdx.x * 3584, 3584);
  }
  if (threadIdx.x == 448) {
    if (blockIdx.x < 6) prefetch_l2((&P.b1)[blockIdx.x], blockIdx.x == 0 ? 3584 : blockIdx.x == 5 ? 4096 : 896);
    prefetch_map(&P.m.bi); prefetch_map(&P.m.x5); prefetch_map(&P.m.nst);
  }
  const uint4 info = P.tab[blockIdx.x];
  uint32_t base = smem_u32(smem_raw);
  asm volatile("mov.u32 %0, %0;" : "+r"(base));
  const uint32_t bars = base + OFF_BAR;
  const int warp = __shfl_sync(0xffffffffu, threadIdx.x >> 5, 0);
  const int lane = threadIdx.x & 31;
  const int cta = blockIdx.x;
  const Maps& M = P.m;
  Scratch* const sc = P.sc;
  uint32_t rank; asm volatile("mov.u32 %0, %%cluster_ctarank;" : "=r"(rank));
  if (warp < 8 || warp == 13) {
    const uint32_t members = __popc((((warp & 2) ? info.z : info.y) >> (16 * (warp & 1))) & 0xffffu);
    const uint32_t cnt = (warp & 12) == 4 ? members : 1u;
    if (elect_one()) {
#pragma unroll
      for (int k = 0; k < 8; k++) mbar_init(bars + 64 * min(warp, 8) + 8 * k, cnt);
      if (warp == 3 || warp == 4) mbar_init(bars + 8 * (B_GOWN - 3 + warp), warp == 3 ? 4 * (info.x >> 22) : 5 * members);
      asm volatile("fence.mbarrier_init.release.cluster;" ::: "memory");
    }
    __syncwarp();
  }
  cluster_arrive_relaxed();
  const int ti = info.x & 15, tj = (info.x >> 4) & 7;
  const int g = lane >> 2, q = lane & 3, o = lane & 7;
  constexpr uint32_t dA0 = desc_lo(1024, 16), dB0 = desc_lo(1024 + 8192, 8192);

  if (warp < 8) {
    const int hf = warp >> 2, w4 = warp & 3, t = threadIdx.x & 127;
    if (warp < 3 && elect_one()) {
#pragma unroll
      for (int k = 0; k < 8; k++) if (k < 7 || warp) mbar_expect_tx(bars + 64 * warp + 8 * k, warp == 1 ? BYTES_B : BYTES_C);
    }
    cluster_wait();
    if (warp < 2 && rank == LEAD(info.w, warp, 0)) {
#pragma unroll 1
      for (int kl = 0; kl < G1A_AHEAD; kl++) {
        if (elect_one()) {
          if (warp) tma5(base + 8192 + kl * SLOT, &M.x5, 64 * kl, ti, bars + 8 * (B_FULLA + kl), info.y >> 16);
          else tma4(base + kl * SLOT, &M.bi, 64 * kl, 8 * tj, bars + 8 * (B_FULLA + kl), info.y & 0xffff);
        }
      }
    }
    asm volatile("setmaxnreg.inc.sync.aligned.u32 160;");
    if (warp == 7) {
      uint32_t* const epp = sc->cnt + (cta < C_TOTAL ? cta * 32 + 1 : (cta - C_TOTAL) * 32 + 2);
      const uint32_t ep = ld_weak(epp) + 1u;
      if (lane == 0) {
        asm volatile("st.shared.u32 [%0], %1;" :: "r"(base + OFF_STAT + 256), "r"(ep) : "memory");
        mbar_arrive(bars + 8 * B_EP);
        *epp = ep;
      }
      __syncwarp();
    } else if ((warp >> 1) == 2) {
      const int brow = 8 * cta + 4 * (warp & 1) + (lane >> 3);
      const __nv_bfloat16* src = (cta < 56 ? P.bre : P.bim - D_ * D_) + brow * D_ + o * 8;
      uint4 bv[7];
#pragma unroll
      for (int c = 0; c < 7; c++) bv[c] = ldg_nc(src + 64 * c);
      float s0 = 0.f, s1 = 0.f;
#pragma unroll
      for (int c = 0; c < 7; c++) {
        s0 += (bf_lo(bv[c].x) + bf_hi(bv[c].x)) + (bf_lo(bv[c].y) + bf_hi(bv[c].y));
        s1 += (bf_lo(bv[c].z) + bf_hi(bv[c].z)) + (bf_lo(bv[c].w) + bf_hi(bv[c].w));
      }
      float bsum = s0 + s1;
      bsum += __shfl_xor_sync(0xffffffffu, bsum, 1); bsum += __shfl_xor_sync(0xffffffffu, bsum, 2); bsum += __shfl_xor_sync(0xffffffffu, bsum, 4);
      GET_EPOCH();
      if (o == 0) asm volatile("{\n.reg .b64 t;\nmov.b64 t, {%1,%2};\nst.relaxed.gpu.global.b64 [%0], t;\n}" :: "l"(sc->stats + S_ + brow), "r"(__float_as_uint(bsum)), "r"(ep & 0xffffu) : "memory");
    }
    uint32_t dsk2 = __byte_perm(ldg_u16(P.dskip + 64 * tj + 16 * w4 + g), ldg_u16(P.dskip + 64 * tj + 16 * w4 + g + 8), 0x5410);
    asm volatile("" : "+r"(dsk2));
    const uint32_t lama = base + OFF_LAM + 16 * (32 * hf + 8 * w4 + g);
    float2 lam, a8, a32, a128, aq;
    uint32_t tr[4], tp[4];
    auto powers = [&]() {
      mbar_wait(bars + 8 * B_LAM, 0);
      lam = lds64(lama);
      float2 w = lam;
#pragma unroll
      for (int u = 0; u < 4; u++) {
        const float2 w1 = cmul(lam, w);
        tr[u] = pack_bf(w.x, w1.x); tp[u] = pack_bf(w.y, w1.y);
        if (u < 3) w = cmul(lam, w1); else a8 = w1;
        asm volatile("" : "+r"(tr[u]), "+r"(tp[u]));
      }
      a32 = csq(csq(a8)); a128 = csq(csq(a32));
      const float2 a512 = csq(csq(a128)), a1024 = csq(a512), one = make_float2(1.f, 0.f);
      aq = cmul((q & 1) ? a512 : one, (q & 2) ? a1024 : one);
      fence_c(a8); fence_c(a32); fence_c(a128); fence_c(aq);
    };
    if (hf) powers();
    else {
      asm volatile("" : "=f"(lam.x), "=f"(lam.y), "=f"(a8.x), "=f"(a8.y), "=f"(a32.x), "=f"(a32.y), "=f"(a128.x), "=f"(a128.y), "=f"(aq.x), "=f"(aq.y));
      asm volatile("" : "=r"(tr[0]), "=r"(tr[1]), "=r"(tr[2]), "=r"(tr[3]), "=r"(tp[0]), "=r"(tp[1]), "=r"(tp[2]), "=r"(tp[3]));
    }
    if (threadIdx.x == 0) TR(31);
    float acc[64];
    do {
    {
      const uint32_t tb = bars + 8 * ((t == 32) == (hf == 1) ? B_EBN : B_EBM), ts = (t == 32) == (hf == 1) ? S_BN : S_BM;
      const uint32_t tgt0 = mapa(tb, LEAD(info.w, ts, 0)), tgt1 = mapa(tb, LEAD(info.w, ts, 1));
      const uint32_t fb = bars + 8 * (hf ? B_FULLA2 : B_FULLA);
      const uint32_t dM = hf ? dA0 + 7 * (SLOT >> 4) : dA0, dMs = hf ? 8192 >> 4 : SLOT >> 4;
      const bool rel = t == 32;
      bool ready = true;
      LT_DECL;
      mbar_wait(fb, 0);
      SCHED_FENCE(17);
      if (hf) named_bar(7, 256); else named_bar(4, 320);
#pragma unroll
      for (int k = 0; k < 7; k++) {
        if (!ready) mbar_wait_mma(fb + 8 * k, 0);
        LT(k, ready);
        if (k == 0 && t == 0) TR(hf ? 29 : 1);
        const uint32_t dA = dM + k * dMs, dB = dA0 + 512 + k * (SLOT >> 4);
        wg_fence();
        wgmma_n128<0, 0>(acc, mkdesc(dA), mkdesc(dB), k);
        wgmma_n128<0, 0>(acc, mkdesc(dA + 2), mkdesc(dB + 2), 1);
        wg_commit();
        wg_wait<1>();
        release_slot(rel && k > 0, ((k & 1) ? tgt0 : tgt1) + 8 * (k - 1), 0);
        if (k == 3) release_slot(hf && (t == 32 || t == 64), tgt1 + 8 * 7, 0);
        ready = mbar_test(fb + 8 * (k + 1), 0);
        wgmma_n128<0, 0>(acc, mkdesc(dA + 4), mkdesc(dB + 4), 1);
        wgmma_n128<0, 0>(acc, mkdesc(dA + 6), mkdesc(dB + 6), 1);
        wg_commit();
      }
      if (hf) asm volatile("bar.arrive 14, 256;" ::: "memory"); else asm volatile("bar.arrive 7, 256;" ::: "memory");
      wg_wait<0>();
      fence_regs(acc);
      release_slot(rel, tgt0 + 8 * 6, 0);
      if (threadIdx.x == 128) mbar_arrive(bars + 8 * B_BDONE);
      if (w4 == 3) LT_DUMP(3, 8 * hf);
    }
    if (t == 0) TR(hf ? 30 : 2);
    if (!hf) powers();
    mbar_wait(bars + 8 * B_STAT, 0);
    uint32_t base2 = base;
    asm volatile("mov.u32 %0, %0;" : "+r"(base2));
    {
      const float2 bs = lds64(lama + 8);
      const uint32_t tg = __float_as_uint(lds32(base2 + OFF_STAT + 256)) & 3u;
      if (!hf) {
        asm volatile("bar.arrive 12, %0;" :: "r"(160u + (__float_as_uint(bs.x) & P.zero)) : "memory");
      } else if (warp == 7) {
        named_bar(12, 160);
        if (elect_one()) {
          mbar_expect_tx(bars + 8 * B_XT, 16384);
          tma2(base + OFF_STG + 8192, &M.xt, 64 * tj, 128 * ti, bars + 8 * B_XT, (uint16_t)(1u << rank));
          tma2(base + OFF_STG + 8192 + 16384 + 256, &M.xt, 64 * tj, 128 * ti + 64, bars + 8 * B_XT, (uint16_t)(1u << rank));
        }
      }
      uint32_t hr[16], hi[16];
      const uint32_t sta = base2 + OFF_STAT + 272 * q;
      float2 h = make_float2(0.f, 0.f);
#pragma unroll
      for (int jj = 0; jj < 16; jj++) {
        const float4 st = lds128(sta + 16 * jj);
        const float2 h0 = cfma(lam, h, make_float2(fmaf(-st.y, bs.x, acc[4 * jj]) * st.x, fmaf(-st.y, bs.y, acc[4 * jj + 2]) * st.x));
        h = cfma(lam, h0, make_float2(fmaf(-st.w, bs.x, acc[4 * jj + 1]) * st.z, fmaf(-st.w, bs.y, acc[4 * jj + 3]) * st.z));
        hr[jj] = pack_bf(h0.x, h.x); hi[jj] = pack_bf(h0.y, h.y);
      }
      uint2* const ebase = sc->E + 64 * tj + 32 * hf + 8 * w4 + g;
      const float2 e0 = make_float2(__shfl_sync(0xffffffffu, h.x, 0, 4), __shfl_sync(0xffffffffu, h.y, 0, 4));
      const float2 e1 = make_float2(__shfl_sync(0xffffffffu, h.x, 1, 4), __shfl_sync(0xffffffffu, h.y, 1, 4));
      const float2 e2 = make_float2(__shfl_sync(0xffffffffu, h.x, 2, 4), __shfl_sync(0xffffffffu, h.y, 2, 4));
      const float2 E = cfma(a32, cfma(a32, cfma(a32, e0, e1), e2), h);
      if (q == 3) asm volatile("{\n.reg .b64 t;\nmov.b64 t, {%1,%2};\nst.relaxed.gpu.global.b64 [%0], t;\n}" :: "l"(ebase + ti * D_), "r"((__float_as_uint(E.x) & ~3u) | tg), "r"(__float_as_uint(E.y)) : "memory");
      SCHED_FENCE(2);
      if (t == 0) TR(hf ? 40 : 4);
      __nanosleep(EWAIT);
      SCHED_FENCE(6);
      const int i0 = ti - 1 - 4 * q;
      uint2 ev[4];
      int it = 0;
#pragma unroll
      for (int k = 0; k < 4; k++) ev[k] = make_uint2(i0 - k >= 0 ? ~tg : tg, 0u);
      while (true) {
#pragma unroll
        for (int k = 0; k < 4; k++)
          asm volatile("{\n.reg .pred p;\n.reg .b64 t;\nsetp.ne.u32 p, %3, 0;\nmov.b64 t, {%0,%1};\n@p ld.relaxed.gpu.global.b64 t, [%2];\nmov.b64 {%0,%1}, t;\n}"
                       : "+r"(ev[k].x), "+r"(ev[k].y) : "l"(ebase + (i0 - k) * D_), "r"((ev[k].x ^ tg) & 3u) : "memory");
        if (__all_sync(0xffffffffu, (((ev[0].x ^ tg) | (ev[1].x ^ tg) | (ev[2].x ^ tg) | (ev[3].x ^ tg)) & 3u) == 0)) break;
        if (++it > SPIN_LIMIT) __trap();
      }
      float2 c = make_float2(__uint_as_float(ev[3].x), __uint_as_float(ev[3].y));
#pragma unroll
      for (int k = 2; k >= 0; k--) c = cfma(a128, c, make_float2(__uint_as_float(ev[k].x), __uint_as_float(ev[k].y)));
      c = cmul(aq, c);
      if (i0 < 0) c = make_float2(0.f, 0.f);
      c.x = (c.x + __shfl_xor_sync(0xffffffffu, c.x, 1)) + (__shfl_xor_sync(0xffffffffu, c.x, 2) + __shfl_xor_sync(0xffffffffu, c.x, 3));
      c.y = (c.y + __shfl_xor_sync(0xffffffffu, c.y, 1)) + (__shfl_xor_sync(0xffffffffu, c.y, 2) + __shfl_xor_sync(0xffffffffu, c.y, 3));
      if (q > 0) c = cfma(a32, c, e0);
      if (q > 1) c = cfma(a32, c, e1);
      if (q > 2) c = cfma(a32, c, e2);
      if (hf) named_bar(15, 256); else mbar_wait(bars + 8 * B_BDONE, 0);
      if (t == 0) TR(hf ? 41 : 5);
      const uint32_t stg = base2 + OFF_STG + (q >> 1) * (16384 + 256) + warp * 2048 + g * 128;
      const uint32_t key = (g + (q & 2)) & 7;
#pragma unroll
      for (int cc = 0; cc < 4; cc++) {
        uint32_t wr[4], wi[4];
        const uint32_t cr = pack_bf(c.x, c.x), ci = pack_bf(c.y, c.y);
        if (cc < 3) c = cmul(a8, c);
#pragma unroll
        for (int u = 0; u < 4; u++) {
          wr[u] = hfma2(tr[u], cr, hfma2(tp[u], ci ^ 0x80008000u, hr[4 * cc + u]));
          wi[u] = hfma2(tr[u], ci, hfma2(tp[u], cr, hi[4 * cc + u]));
        }
        const uint32_t a = stg + ((((q & 1) * 4 + cc) ^ key) << 4);
        asm volatile("st.shared.v4.u32 [%0], {%1,%2,%3,%4};" :: "r"(a), "r"(wr[0]), "r"(wr[1]), "r"(wr[2]), "r"(wr[3]) : "memory");
        asm volatile("st.shared.v4.u32 [%0], {%1,%2,%3,%4};" :: "r"(a + 1024), "r"(wi[0]), "r"(wi[1]), "r"(wi[2]), "r"(wi[3]) : "memory");
      }
      fence_async_smem();
      if (hf) asm volatile("bar.arrive 5, 160;" ::: "memory"); else asm volatile("bar.arrive 1, 160;" ::: "memory");
      if (t == 0) TR(hf ? 42 : 6);
    }
    if (hf) break;
    {
      uint32_t xr[32];
      mbar_wait(bars + 8 * B_XT, 0);
      const uint32_t ch = 2 * warp + ((lane >> 3) & 1), a0 = base2 + OFF_STG + 8192 + (8 * (lane >> 4) + o) * 128;
#pragma unroll
      for (int jj = 0; jj < 16; jj += 2) {
        asm volatile("ldmatrix.sync.aligned.m8n8.x4.trans.shared.b16 {%0,%1,%2,%3}, [%4];"
                     : "=r"(xr[2 * jj]), "=r"(xr[2 * jj + 1]), "=r"(xr[2 * jj + 2]), "=r"(xr[2 * jj + 3])
                     : "r"(a0 + (jj & 7) * 1024 + (jj >> 3) * (16384 + 256) + ((ch ^ ((o + 2 * (jj >> 3)) & 7)) << 4)));
      }
      const uint32_t dep = ((xr[0] | xr[4] | xr[8]) | (xr[12] | xr[16] | xr[20]) | (xr[24] | xr[28])) & P.zero;
      asm volatile("bar.arrive 15, %0;" :: "r"(256u + dep) : "memory");
#pragma unroll
      for (int jj = 0; jj < 16; jj++) {
        if (jj) {
          float d; asm("ex2.approx.ftz.f32 %0, %1;" : "=f"(d) : "f"(acc[4 * jj - 1]));
#pragma unroll
          for (int k = 2 * jj; k < 2 * jj + 2; k++) xr[k] |= __float_as_uint(d) & P.zero;
        }
        const float4 st = lds128(base2 + OFF_STAT + 8 * (8 * jj + 2 * q + 2 * (jj >> 2)));
        const uint32_t b2 = __float_as_uint(lds32(base2 + OFF_B2 + 2 * (8 * jj + 2 * q)));
        const uint32_t m2 = __byte_perm(__float_as_uint(st.y), __float_as_uint(st.w), 0x7632), r2 = pack_bf(st.x, st.z);
#pragma unroll
        for (int s = 0; s < 2; s++) {
          const uint32_t x2 = xr[2 * jj + s];
          const uint32_t tt = hfma2(hmul2(hsub2(x2, m2), r2), __byte_perm(dsk2, 0, s ? 0x3232 : 0x1010), b2);
          acc[4 * jj + 2 * s]     = bf_lo(x2) + bf_lo(tt);
          acc[4 * jj + 2 * s + 1] = bf_hi(x2) + bf_hi(tt);
        }
      }
    }
    fence_regs(acc);
    if (t == 0) TR(8);
    {
      const bool rel = lane == 0 && warp < 3;
      const uint32_t tb = bars + 8 * (warp == 0 ? B_FULLC : warp == 1 ? B_ECM : B_ECN);
      const uint32_t tgt0 = mapa(tb, warp == 0 ? rank : LEAD(info.w, (warp - 1) & 1, 0)), tgt1 = mapa(tb, warp == 0 ? rank : LEAD(info.w, (warp - 1) & 1, 1));
      const uint32_t tx = warp == 0 ? BYTES_C : 0;
      bool ready = true;
      LT_DECL;
      mbar_wait(bars + 8 * B_FULLC, 0);
      SCHED_FENCE(18);
      named_bar(8, 256);
#define G2_BLOCK(TA, ADV, COND)                                                              \
        const uint32_t s = m & 7;                                                            \
        if (!ready) mbar_wait_mma(bars + 8 * B_FULLC + 8 * s, (m >> 3) & 1);                     \
        LT(m, ready);                                                                        \
        const uint32_t dA = dA0 + s * (SLOT >> 4), dB = dB0 + s * (SLOT >> 4);               \
        wg_fence();                                                                          \
        wgmma_n128<TA, 1>(acc, mkdesc(dA), mkdesc(dB), 1);                                   \
        wgmma_n128<TA, 1>(acc, mkdesc(dA + ADV), mkdesc(dB + 128), 1);                       \
        wg_commit();                                                                         \
        wg_wait<1>();                                                                        \
        release_slot(rel && (COND), ((m & 1) ? tgt0 : tgt1) + 8 * ((m - 1) & 7), tx);        \
        ready = mbar_test(bars + 8 * B_FULLC + 8 * ((m + 1) & 7), ((m + 1) >> 3) & 1);       \
        wgmma_n128<TA, 1>(acc, mkdesc(dA + 2 * ADV), mkdesc(dB + 256), 1);                   \
        wgmma_n128<TA, 1>(acc, mkdesc(dA + 3 * ADV), mkdesc(dB + 384), 1);                   \
        wg_commit();
#pragma unroll 1
      for (int m = 0; m < 14; m++) { G2_BLOCK(0, 2, m > 0) }
#pragma unroll 1
      for (int m = 14; m < 42 - TAILK; m++) { G2_BLOCK(1, 128, m < 35) }
      const int dc = 16 * (warp & 1) + g;
      const uint32_t stg = base2 + OFF_STG + (warp >> 1) * 16384 + (dc & 3) * 4;
      auto store_chunk = [&](int c) {
#pragma unroll
        for (int k = 16 * c; k < 16 * c + 16; k++) {
          const int sr = 2 * q + (k & 1);
          asm volatile("st.shared.f32 [%0], %1;" :: "r"(stg + (8 * (k >> 2) + sr) * 128 + ((((dc >> 2) + (k & 2)) ^ sr) << 4)), "f"(acc[k]) : "memory");
        }
        fence_async_smem();
        if (warp < 2) named_bar(2, 64); else named_bar(3, 64);
        if (!(warp & 1) && elect_one()) {
          tma_st2(&M.ost, base + OFF_STG + (warp >> 1) * 16384 + c * 4096, 64 * tj + 32 * (warp >> 1), 128 * ti + 32 * c);
          bulk_commit();
        }
      };
      float tL[32], tR[32];
      static_assert(TAILK >= 2 && TAILK < 8, "no slot is released below");
#pragma unroll
      for (int m = 42 - TAILK; m < 42; m++) {
        const uint32_t s = m & 7;
        if (!ready) mbar_wait_mma(bars + 8 * B_FULLC + 8 * s, (m >> 3) & 1);
        LT(m, ready);
        const uint32_t dA = dA0 + s * (SLOT >> 4), dB = dB0 + s * (SLOT >> 4);
        wg_fence();
        wgmma_n64<1, 1>(tL, mkdesc(dA), mkdesc(dB), m - (42 - TAILK));
        ready = mbar_test(bars + 8 * B_FULLC + 8 * ((m + 1) & 7), ((m + 1) >> 3) & 1);
        wgmma_n64<1, 1>(tL, mkdesc(dA + 128), mkdesc(dB + 128), 1);
        wgmma_n64<1, 1>(tL, mkdesc(dA + 256), mkdesc(dB + 256), 1);
        wgmma_n64<1, 1>(tL, mkdesc(dA + 384), mkdesc(dB + 384), 1);
        wg_commit();
      }
      auto right = [&](int m, int first) {
        const uint32_t s = m & 7, dA = dA0 + s * (SLOT >> 4), dB = dB0 + s * (SLOT >> 4) + 512;
        wg_fence();
#pragma unroll
        for (int kk = 0; kk < 4; kk++) wgmma_n64<1, 1>(tR, mkdesc(dA + 128 * kk), mkdesc(dB + 128 * kk), kk || !first);
        wg_commit();
      };
      right(42 - TAILK, 1);
      wg_wait<1>();
      fence_regs(acc); fence_regs(tL);
#pragma unroll
      for (int k = 0; k < 16; k++) acc[k] += tL[k];
      store_chunk(0);
      right(43 - TAILK, 0);
#pragma unroll
      for (int k = 16; k < 32; k++) acc[k] += tL[k];
      store_chunk(1);
#pragma unroll 1
      for (int m = 44 - TAILK; m < 42; m++) right(m, 0);
      wg_wait<0>();
      fence_regs(tR);
#pragma unroll
      for (int k = 0; k < 32; k++) acc[32 + k] += tR[k];
      if (t == 0) TR(14);
      if (warp == 3) LT_DUMP(0, 32);
      store_chunk(2); store_chunk(3);
    }
    } while (P.zero & (1u << 29));
    cluster_arrive_relaxed();
    bulk_wait_read0();
    if (threadIdx.x == 0) TR(15);
    cluster_wait();
  } else {
    asm volatile("setmaxnreg.dec.sync.aligned.u32 96;");
    const int row = 128 * ti + 4 * (warp < 12 ? 4 * tj + warp - 8 : 28 + tj) + (lane >> 3);
    const bool hasRow = warp < 12 || (warp == 12 && tj < 4);
    uint4 v[7];
    if (hasRow) {
      const __nv_bfloat16* src = P.x + row * D_ + o * 8;
#pragma unroll
      for (int c = 0; c < 7; c++) v[c] = ldg_nc(src + 64 * c);
    } else {
#pragma unroll
      for (int c = 0; c < 7; c++) asm volatile("" : "=r"(v[c].x), "=r"(v[c].y), "=r"(v[c].z), "=r"(v[c].w));
    }
    SCHED_FENCE(7);
    if (warp < 14) {
      if (warp == 13 && elect_one()) {
#pragma unroll
        for (int k = 0; k < 7; k++) mbar_expect_tx(bars + 8 * (B_FULLA2 + k), 8192);
      }
      float c0[4] = {0.f, 0.f, 0.f, 0.f}, c1[4] = {0.f, 0.f, 0.f, 0.f};
#pragma unroll
      for (int c = 0; c < 7; c++) mma16816((c & 1) ? c1 : c0, v[c].x, v[c].y, v[c].z, v[c].w, 0x3f803f80u, 0x3f803f80u);
      float sum = (c0[0] + c0[2]) + (c1[0] + c1[2]);
      sum += __shfl_xor_sync(0xffffffffu, sum, 4);
      const float mean = sum * (1.f / D_);
      const uint32_t mb2 = pack_bf(mean, mean);
      const float mb = bf_hi(mb2), dm = mean - mb;
      float c2[4] = {0.f, 0.f, 0.f, 0.f}, c3[4] = {0.f, 0.f, 0.f, 0.f}, c4[4] = {0.f, 0.f, 0.f, 0.f}, c5[4] = {0.f, 0.f, 0.f, 0.f};
#pragma unroll
      for (int c = 0; c < 7; c++) {
        v[c].x = hsub2(v[c].x, mb2); v[c].y = hsub2(v[c].y, mb2); v[c].z = hsub2(v[c].z, mb2); v[c].w = hsub2(v[c].w, mb2);
        mma1688(c2, v[c].x, v[c].y, v[c].x); mma1688(c3, v[c].x, v[c].y, v[c].y);
        mma1688(c4, v[c].z, v[c].w, v[c].z); mma1688(c5, v[c].z, v[c].w, v[c].w);
      }
      float ss = (lane & 4) ? (c2[1] + c3[3]) + (c4[1] + c5[3]) : (c2[0] + c3[2]) + (c4[0] + c5[2]);
      ss = __shfl_sync(0xffffffffu, ss, (lane & 28) | (lane >> 3));
      ss += __shfl_xor_sync(0xffffffffu, ss, 4);
      const float var = fmaxf(fmaf(ss, 1.f / D_, -dm * dm), 0.f);
      const float r1 = rsqrtf(var + 1e-5f);
      const float a = r1 * rsqrtf(fmaf(var * r1, r1, 1e-5f)), b = -dm * a;
      const uint32_t ah = pack_bf(a, a), al = pack_bf(a - bf_hi(ah), a - bf_hi(ah)), b2 = pack_bf(b, b);
      const uint32_t lst = base + OFF_STG + 8192 + (warp - 8) * 3584;
#pragma unroll
      for (int c = 0; c < 7; c++) {
        uint4 w;
        w.x = hfma2(v[c].x, ah, hfma2(v[c].x, al, b2)); w.y = hfma2(v[c].y, ah, hfma2(v[c].y, al, b2));
        w.z = hfma2(v[c].z, ah, hfma2(v[c].z, al, b2)); w.w = hfma2(v[c].w, ah, hfma2(v[c].w, al, b2));
        asm volatile("{\n.reg .pred p;\nsetp.ne.u32 p, %0, 0;\n@p st.shared.v4.u32 [%1], {%2,%3,%4,%5};\n}"
                     :: "r"((uint32_t)hasRow), "r"(lst + (lane >> 3) * 896 + o * 16 + c * 128), "r"(w.x), "r"(w.y), "r"(w.z), "r"(w.w) : "memory");
      }
      fence_async_smem();
      __syncwarp();
      if (hasRow && elect_one()) { tma_st3(&M.nst, lst, 0, 0, row); bulk_commit(); }
      asm volatile("bar.arrive 4, 320;" ::: "memory");
      if (threadIdx.x == 256) TR(33);
      SCHED_FENCE(27);
      cluster_wait();
      if (warp < 13) {
        GET_EPOCH();
        if (hasRow && o == 0)
          asm volatile("{\n.reg .b64 t;\nmov.b64 t, {%1,%2};\nst.relaxed.gpu.global.b64 [%0], t;\n}" :: "l"(sc->stats + row), "r"(__float_as_uint(r1)), "r"((mb2 & 0xffff0000u) | (ep & 0xffffu)) : "memory");
        SCHED_FENCE(9);
        bulk_wait_read0();
        __syncwarp();
        release_slot(lane == 0, mapa(bars + 8 * B_LNM, LEAD(info.w, S_AM, 1)), 0);
        bulk_wait0();
        if (hasRow && elect_one()) red_relaxed(sc->cnt + (C_LN + ti) * 32);
        __syncwarp();
      }
    }
    const int ft = (info.x >> 7) & 31, dt = (info.x >> 12) & 3;
    const int rot = (info.x >> 14) & 31, own = (info.x >> 19) & 7, csize = info.x >> 22;
    if (warp < 12 || warp == 13) {
      const int w = warp - 8, t = threadIdx.x - 256;
      const bool real = warp < 12;
      float acc[56];
      if (!real) {
      {
        const bool lx = rank == LEAD(info.w, S_AN, 0), la = rank == LEAD(info.w, S_AM, 0), lb = rank == LEAD(info.w, S_AM, 1);
        mbar_wait(bars + 8 * B_FULLA, 0);
#pragma unroll 1
        for (int kl = G1A_AHEAD; kl < 7; kl++) {
          if (lx && elect_one()) tma5(base + 8192 + kl * SLOT, &M.x5, 64 * kl, ti, bars + 8 * (B_FULLA + kl), info.y >> 16);
          if (la && elect_one()) tma4(base + kl * SLOT, &M.bi, 64 * kl, 8 * tj, bars + 8 * (B_FULLA + kl), info.y & 0xffff);
        }
        if (lb) {
#pragma unroll 1
          for (int kl = 0; kl < 7; kl++) {
            if (kl == 4) mbar_wait(bars + 8 * B_LNM, 0);
            if (elect_one()) tma4(base + 7 * SLOT + kl * 8192, &M.bi, 64 * kl, 8 * tj + 4, bars + 8 * (B_FULLA2 + kl), info.y & 0xffff);
          }
        }
      }
      if ((rank == LEAD(info.w, S_BM, 0)) != (rank == LEAD(info.w, S_BM, 1))) {
        const int odd = rank == LEAD(info.w, S_BM, 1);
        const uint32_t d0 = base + odd * SLOT, f0 = bars + 8 * (B_FULLB + odd);
        run_half(odd, bars + 8 * B_EBM, [&](int r, int k) {
          const int y = 512 * r + 64 * odd + 128 * k;
          tma2(d0 + 2 * k * SLOT, &M.w1, 64 * ft, y, f0 + 16 * k, info.z & 0xffff);
          if (r < 3) tma_pf2(&M.w1, 64 * ft, y + 64 * PF_W1);
        });
      } else if (rank == LEAD(info.w, S_BM, 0)) {
        int n = 0; uint32_t lt0, lt1;
        run_seg(n, 1, 32, bars + 8 * B_EBM, lt0, lt1, [&](int n) {
          tma2(base + (n & 7) * SLOT, &M.w1, 64 * ft, 64 * n, bars + 8 * B_FULLB + 8 * (n & 7), info.z & 0xffff);
        });
      }
#pragma unroll
        for (int k = 0; k < 56; k++) asm volatile("" : "=f"(acc[k]));
      } else {
      if (t == 0) TR(16);
      const uint32_t b10 = ldg_u16(P.b1 + 64 * ft + 16 * w + g), b11 = ldg_u16(P.b1 + 64 * ft + 16 * w + g + 8);
      if (w < 2) {
        GET_EPOCH();
        const int pl = t, p = 64 * tj + pl;
        {
          uint4 st; uint2 br, bi;
          int it = 0;
          while (true) {
            asm volatile("{\n.reg .b64 t, u;\nld.relaxed.gpu.global.v2.b64 {t, u}, [%4];\nmov.b64 {%0,%1}, t;\nmov.b64 {%2,%3}, u;\n}" : "=r"(st.x), "=r"(st.y), "=r"(st.z), "=r"(st.w) : "l"(sc->stats + 128 * ti + 2 * pl) : "memory");
            asm volatile("{\n.reg .b64 t;\nld.relaxed.gpu.global.b64 t, [%2];\nmov.b64 {%0,%1}, t;\n}" : "=r"(br.x), "=r"(br.y) : "l"(sc->stats + S_ + p + (P.swap ? D_ : 0)) : "memory");
            asm volatile("{\n.reg .b64 t;\nld.relaxed.gpu.global.b64 t, [%2];\nmov.b64 {%0,%1}, t;\n}" : "=r"(bi.x), "=r"(bi.y) : "l"(sc->stats + S_ + p + (P.swap ? 0 : D_)) : "memory");
            if (__all_sync(0xffffffffu, (((st.y ^ ep) | (st.w ^ ep) | (br.y ^ ep) | (bi.y ^ ep)) & 0xffffu) == 0)) break;
            __nanosleep(50);
            if (++it > SPIN_LIMIT) __trap();
          }
          asm volatile("st.shared.v4.u32 [%0], {%1,%2,%3,%4};" :: "r"(base + OFF_STAT + 16 * (pl + (pl >> 4))), "r"(st.x), "r"(st.y & 0xffff0000u), "r"(st.z), "r"(st.w & 0xffff0000u) : "memory");
          named_bar(9, 128);
          asm volatile("st.shared.v2.u32 [%0], {%1,%2};" :: "r"(base + OFF_LAM + 16 * pl + 8), "r"(br.x), "r"(bi.x) : "memory");
        }
        named_bar(10, 64);
        if (t == 0) { mbar_arrive(bars + 8 * B_STAT); TR(28); }
      }
#pragma unroll
      for (int k = 0; k < 56; k++) acc[k] = bf_lo((k & 2) ? b11 : b10);
      fence_regs(acc);
      {
        const bool rel = lane == 0 && w < 3;
        const uint32_t tb = bars + 8 * (w == 0 ? B_FULLB : w == 1 ? B_EBM : B_EBN), tc = bars + 8 * (w == 1 ? B_ECM : B_ECN);
        uint32_t tgt0 = mapa(tb, w == 0 ? rank : LEAD(info.w, (w + 1) & 3, 0)), tgt1 = mapa(tb, w == 0 ? rank : LEAD(info.w, (w + 1) & 3, 1));
        const uint32_t tgtC0 = mapa(tc, LEAD(info.w, (w - 1) & 1, 0)), tgtC1 = mapa(tc, LEAD(info.w, (w - 1) & 1, 1));
        const uint32_t tx = w == 0 ? BYTES_B : 0;
        bool ready = true;
        LT_DECL;
        mbar_wait(bars + 8 * B_FULLB, 0);
        SCHED_FENCE(19);
        named_bar(14, 256);
        bool p7 = false;
        const uint32_t t7 = tgt1;
#pragma unroll 1
        for (int r = 0; r < 4; r++) {
          const uint32_t par = r & 1;
          if (r == 3) { tgt0 = tgtC0; tgt1 = tgtC1; }
          const bool pr = rel && (r < 3 || w > 0);
#pragma unroll
          for (int s = 0; s < 8; s++) {
            if (!ready) mbar_wait_mma(bars + 8 * B_FULLB + 8 * s, par);
            LT(8 * r + s, ready);
            const uint32_t dA = dA0 + s * (SLOT >> 4), dB = dB0 + s * (SLOT >> 4);
            wg_fence();
            wgmma_n112<1, 1>(acc, mkdesc(dA), mkdesc(dB), 1);
            wgmma_n112<1, 1>(acc, mkdesc(dA + 128), mkdesc(dB + 128), 1);
            wg_commit();
            wg_wait<1>();
            if (s == 0) release_slot(p7, t7 + 8 * 7, tx); else release_slot(pr, ((s & 1) ? tgt0 : tgt1) + 8 * (s - 1), tx);
            ready = mbar_test(bars + 8 * B_FULLB + 8 * ((s + 1) & 7), s == 7 ? par ^ 1 : par);
            wgmma_n112<1, 1>(acc, mkdesc(dA + 256), mkdesc(dB + 256), 1);
            wgmma_n112<1, 1>(acc, mkdesc(dA + 384), mkdesc(dB + 384), 1);
            wg_commit();
          }
          p7 = pr;
        }
        wg_wait<0>();
        release_slot(rel && w > 0, tgtC1 + 8 * 7, 0);
        if (w == 3) LT_DUMP(0, 0);
        fence_regs(acc);
      }
      }
      LT_DECL;
      LT(0, 0);
      if (t == 96) TR(22);
      {
      mbar_wait(bars + 8 * B_HREAD, 0);
      LT(1, 0);
      const uint32_t stg = base + OFF_STG + (w >> 1) * (16384 + 256) + (w & 1) * 4096;
      {
        const uint32_t a0 = stg + (lane & 15) * 224 + (lane >> 4) * 16;
        constexpr int GLA = 4, GLB = 6;
        float z[56];
#pragma unroll
        for (int k = 0; k < GLA; k++) z[k] = acc[k] * fmaf(acc[k] * acc[k], 0.044715f * 0.7978845608f, 0.7978845608f);
#pragma unroll
        for (int k = 0; k < 56 + GLB; k++) {
          if (k < 56) asm volatile("tanh.approx.f32 %0, %0;" : "+f"(z[k]));
          if (k + GLA < 56) {
            const int n = k + GLA;
            asm volatile("{\n.reg .f32 t;\nmul.f32 t, %1, %1;\nfma.rn.f32 t, t, 0f3D122279, 0f3F4C422A;\nmul.f32 %0, t, %1;\n}" : "=f"(z[n]) : "f"(acc[n]));
          }
          if (k >= GLB) {
            const int n = k - GLB;
            asm volatile("{\n.reg .f32 t;\nmul.f32 t, %1, 0f3F000000;\nfma.rn.f32 %0, t, %0, t;\n}" : "+f"(z[n]) : "f"(acc[n]));
            if ((n & 7) == 7) {
              const int j = n >> 3;
              asm volatile("{\n.reg .pred p;\nsetp.ne.u32 p, %5, 0;\n@p stmatrix.sync.aligned.m8n8.x4.shared.b16 [%0], {%1,%2,%3,%4};\n}" :: "r"(a0 + j * 32),
                           "r"(pack_bf(z[n - 7], z[n - 6])), "r"(pack_bf(z[n - 5], z[n - 4])), "r"(pack_bf(z[n - 3], z[n - 2])), "r"(pack_bf(z[n - 1], z[n])), "r"((uint32_t)real) : "memory");
              if (j == 6 && real) asm volatile("bar.arrive 8, 256;" ::: "memory");
            }
          }
          if (k % 14 == 13 && (P.zero >> 8 == 77 + k)) __trap();
        }
      }
      }
      LT(2, 0);
      if (real) {
      const uint32_t stg = base + OFF_STG + (w >> 1) * (16384 + 256) + (w & 1) * 4096;
      fence_async_smem();
      __syncwarp();
      if (elect_one()) { tma_st2(&M.gst, stg, 112 * dt, 64 * ft + 16 * w); bulk_commit(); }
      LT(3, 0);
      if (w == 1) LT_DUMP(3, 16);
      if (elect_one()) {
        bulk_wait0();
        red_relaxed(sc->cnt + (C_G + ft) * 32);
        TR(w == 0 ? 23 : 43 + w);
      }
      __syncwarp();
      release_slot(lane < csize, mapa(bars + 8 * B_GOWN, lane & (csize - 1)), 0);
      } else {
      GET_EPOCH();
      mbar_wait(bars + 8 * B_GOWN, 0);
      poll_counters(sc->cnt, C_G, 28, ep * 16u, lane);
      if (lane == 0) TR(26);
      if (lane == 0) mbar_arrive(bars + 8 * B_GALL);
      }
    } else if (warp == 12) {
      GET_EPOCH();
      if (elect_one()) {
        prefetch_map(&M.w1); prefetch_map(&M.hn64); prefetch_map(&M.hn48); prefetch_map(&M.hld);
        prefetch_map(&M.xt); prefetch_map(&M.w2); prefetch_map(&M.cld); prefetch_map(&M.gld); prefetch_map(&M.hst); prefetch_map(&M.gst); prefetch_map(&M.ost);
      }
      __syncwarp();
      if (rank == LEAD(info.w, S_BN, 0) || rank == LEAD(info.w, S_BN, 1)) poll_counters(sc->cnt, C_LN, 16, ep * 32u, lane);
      if (lane == 0) TR(19);
      if ((rank == LEAD(info.w, S_BN, 0)) != (rank == LEAD(info.w, S_BN, 1))) {
        const int odd = rank == LEAD(info.w, S_BN, 1);
        const uint32_t d0 = base + odd * SLOT + 8192, f0 = bars + 8 * (B_FULLB + odd);
        run_half(odd, bars + 8 * B_EBN, [&](int r, int k) {
          const int y = dt * S_ + 512 * r + 64 * odd + 128 * k;
          tma2(d0 + 2 * k * SLOT, &M.hn64, 0, y, f0 + 16 * k, info.z >> 16);
          tma2(d0 + 2 * k * SLOT + 8192, &M.hn48, 64, y, f0 + 16 * k, info.z >> 16);
        });
      } else if (rank == LEAD(info.w, S_BN, 0)) {
        int n = 0; uint32_t lt0, lt1;
        run_seg(n, 1, 32, bars + 8 * B_EBN, lt0, lt1, [&](int n) {
          tma2(base + (n & 7) * SLOT + 8192, &M.hn64, 0, dt * S_ + 64 * n, bars + 8 * B_FULLB + 8 * (n & 7), info.z >> 16);
          tma2(base + (n & 7) * SLOT + 16384, &M.hn48, 64, dt * S_ + 64 * n, bars + 8 * B_FULLB + 8 * (n & 7), info.z >> 16);
        });
      }
      const bool l0 = rank == LEAD(info.w, S_AN, 0), l1 = rank == LEAD(info.w, S_AN, 1);
      if (l0 || l1) {
        const int step = l0 && l1 ? 1 : 2;
        int m = l0 ? 0 : 1;
        uint32_t lt0 = 0, lt1 = 0;
#pragma unroll 1
        for (int seg = 0; seg < 4; seg++) {
          if (seg == 0) { mbar_wait(bars + 8 * B_HREAD, 0); poll_counters(sc->cnt, C_H + ti, 1, ep * 7u, lane); }
          if (seg == 1) mbar_wait(bars + 8 * B_H1, 0);
          if (lane == 0 && seg == 0) TR(27);
          const int off = seg < 2 ? 0 : seg == 2 ? rot - 14 : rot - 42;
          const CUtensorMap* mp = seg < 2 ? &M.hld : &M.w2;
          run_seg(m, step, seg == 0 ? 7 : seg == 1 ? 14 : seg == 2 ? 42 - rot : 42, bars + 8 * B_ECN, lt0, lt1, [&](int m) {
            tma3(base + (m & 7) * SLOT + 8192, mp, 0, 64 * (m + off), 2 * ti, bars + 8 * B_FULLC + 8 * (m & 7), info.y >> 16);
            if ((uint32_t)(m - 14 + PF_W2) < 28u) { const int f2 = m - 14 + PF_W2 + rot; tma_pf3(&M.w2, 0, 64 * (f2 >= 28 ? f2 - 28 : f2), 2 * ti); }
          });
        }
        LT_DUMP(2, 32);
      }
    } else {
      const int hw = warp - 14, pl = threadIdx.x & 63, p = 64 * tj + pl;
      if ((base & 0x3ffffu) != 1024u) __trap();
      {
        const float lre = bf_lo(ldg_u16(P.lre + p)), lim = bf_lo(ldg_u16(P.lim + p));
        const float dtv = bfr(expf(bf_lo(ldg_u16(P.logdt + p))));
        const uint32_t b2w = __ldg(reinterpret_cast<const uint32_t*>(P.b2) + 64 * ti + pl);
        float th = dtv * lim;
        const float kq = rintf(th * 0.15915494309f);
        th = fmaf(kq, -6.28318548202514648f, th); th = fmaf(kq, 1.74845553e-7f, th);
        const float mag = expf(dtv * lre);
        const float2 lam = make_float2(mag * __cosf(th), mag * __sinf(th));
        const float inv = 2.f * rcp_fast(lre * lre + lim * lim), nr = lam.x - 1.f, ni = lam.y;
        asm volatile("st.shared.u32 [%0], %1;" :: "r"(base + OFF_B2 + 4 * pl), "r"(b2w) : "memory");
        asm volatile("st.shared.v4.f32 [%0], {%1,%2,%3,%4};" :: "r"(base + OFF_LAM + 16 * pl), "f"(lam.x), "f"(P.swap ? -lam.y : lam.y),
                     "f"((nr * lre + ni * lim) * inv), "f"((ni * lre - nr * lim) * inv) : "memory");
      }
      cluster_wait();
      named_bar(6, 64);
      if (pl == 0) { mbar_arrive(bars + 8 * B_LAM); TR(37); }
      uint32_t xh[4], xl[4], yh[4], yl[4];
#pragma unroll
      for (int u = 0; u < 4; u++) {
        const float2 c0 = lds64(base + OFF_LAM + 16 * (8 * o + 2 * u) + 8), c1 = lds64(base + OFF_LAM + 16 * (8 * o + 2 * u + 1) + 8);
        xh[u] = pack_bf(c0.x, c1.x); xl[u] = pack_bf(c0.x - bf_lo(xh[u]), c1.x - bf_hi(xh[u]));
        yh[u] = pack_bf(-c0.y, -c1.y); yl[u] = pack_bf(-c0.y - bf_lo(yh[u]), -c1.y - bf_hi(yh[u]));
        asm volatile("" : "+r"(xh[u]), "+r"(xl[u]), "+r"(yh[u]), "+r"(yl[u]));
      }
      GET_EPOCH();
      asm volatile("bar.arrive 9, %0;" :: "r"(128u + ((xl[0] | xl[1] | xl[2] | xl[3]) & P.zero)) : "memory");
      mbar_wait(bars + 8 * B_FULLA, 0);
      {
        uint4 cv[4][2];
        const int crow = 28 * ti + (pl >> 3);
#pragma unroll
        for (int k = 0; k < 4; k++) {
          const int off = (crow + (k < 3 || !hw ? 8 * k : 0)) * D_ + 64 * tj + 8 * o;
          cv[k][0] = ldg_nc(P.cre + off); cv[k][1] = ldg_nc(P.cim + off);
        }
        uint4* dst = reinterpret_cast<uint4*>(sc->cp + crow * 896 + 64 * tj) + 56 * (o >> 2) + 2 * (o & 3);
#pragma unroll 1
        for (int k = 0; k < 4 - hw; k++) {
          const uint32_t cr[4] = {cv[0][0].x, cv[0][0].y, cv[0][0].z, cv[0][0].w}, ci[4] = {cv[0][1].x, cv[0][1].y, cv[0][1].z, cv[0][1].w};
          uint32_t wr[4], wi[4];
#pragma unroll
          for (int u = 0; u < 4; u++) {
            const uint32_t ni = ci[u] ^ 0x80008000u;
            wr[u] = hfma2(xh[u], cr[u], hfma2(yh[u], ci[u], hfma2(yl[u], ci[u], hmul2(xl[u], cr[u]))));
            wi[u] = hfma2(xh[u], ni, hfma2(yh[u], cr[u], hfma2(yl[u], cr[u], hmul2(xl[u], ni))));
          }
          dst[k * 896 + P.swap] = make_uint4(wr[0], wr[1], wr[2], wr[3]);
          dst[k * 896 + 1 - P.swap] = make_uint4(wi[0], wi[1], wi[2], wi[3]);
#pragma unroll
          for (int u = 0; u < 3; u++) { cv[u][0] = cv[u + 1][0]; cv[u][1] = cv[u + 1][1]; }
        }
      }
      if (lane == 0) TR(36);
      if (hw) {
        asm volatile("bar.arrive 6, 64;" ::: "memory");
#pragma unroll 1
        for (int s = 0; s < 2; s++) {
          if (s == 0) named_bar(1, 160); else named_bar(5, 160);
          if (elect_one()) {
#pragma unroll
            for (int c = 0; c < 4; c++) {
              const int sub = c & 1, w0 = (c >> 1) * 2;
              tma_st3(&M.hst, base + OFF_STG + sub * (16384 + 256) + (4 * s + w0) * 2048, 0, 448 * s + 64 * tj + 16 * w0, 2 * ti + sub);
              bulk_commit();
              if (c < 3) {
                asm volatile("cp.async.bulk.wait_group.read 1;" ::: "memory");
                __nanosleep(HGAP);
              }
            }
            bulk_wait0();
            red_relaxed(sc->cnt + (C_H + 16 * s + ti) * 32);
            TR(s ? 7 : 3);
            if (s == 0) mbar_arrive(bars + 8 * B_HREAD);
          }
          __syncwarp();
        }
        poll_counters(sc->cnt, C_H + 16 + ti, 1, ep * 7u, lane);
        if (lane == 0) mbar_arrive(bars + 8 * B_H1);
      } else {
        named_bar(6, 64);
        if (lane == 0) { red_release(sc->cnt + (C_C + tj) * 32); TR(35); }
        __syncwarp();
        const bool l0 = rank == LEAD(info.w, S_AM, 0), l1 = rank == LEAD(info.w, S_AM, 1);
        if (l0 || l1) {
          mbar_wait(bars + 8 * B_HREAD, 0);
          poll_counters(sc->cnt, C_C, 7, ep * 16u, lane);
          fence_async_global();
          if (lane == 0) TR(34);
          const int step = l0 && l1 ? 1 : 2;
          int m = l0 ? 0 : 1;
          uint32_t lt0 = 0, lt1 = 0;
          run_seg(m, step, 14, bars + 8 * B_ECM, lt0, lt1, [&](int m) {
            tma2(base + (m & 7) * SLOT, &M.cld, 64 * m, 64 * tj, bars + 8 * B_FULLC + 8 * (m & 7), info.y & 0xffff);
          });
#pragma unroll 1
          for (int seg = 0; seg < 3; seg++) {
            mbar_wait(bars + 8 * (seg ? B_GALL : B_GOWN), 0);
            if (lane == 0 && seg == 0) TR(25);
            const int off = seg == 2 ? rot - 42 : rot - 14;
            run_seg(m, step, seg == 0 ? 14 + own : seg == 1 ? 42 - rot : 42, bars + 8 * B_ECM, lt0, lt1, [&](int m) {
              tma2(base + (m & 7) * SLOT, &M.gld, 64 * tj, 64 * (m + off), bars + 8 * B_FULLC + 8 * (m & 7), info.y & 0xffff);
            });
          }
          LT_DUMP(1, 32);
        }
      }
    }
    __syncwarp();
    cluster_arrive_relaxed();
    cluster_wait();
  }
}

typedef CUresult (*EncodeFn)(CUtensorMap*, CUtensorMapDataType, cuuint32_t, void*, const cuuint64_t*, const cuuint64_t*, const cuuint32_t*,
                             const cuuint32_t*, CUtensorMapInterleave, CUtensorMapSwizzle, CUtensorMapL2promotion, CUtensorMapFloatOOBfill);

void encode(EncodeFn fn, CUtensorMap* m, CUtensorMapDataType ty, int rank, const void* ptr, const cuuint64_t* dims, const cuuint64_t* strides,
            const cuuint32_t* box, CUtensorMapSwizzle sw) {
  cuuint32_t es[5] = {1, 1, 1, 1, 1};
  fn(m, ty, rank, const_cast<void*>(ptr), dims, strides, box, es, CU_TENSOR_MAP_INTERLEAVE_NONE, sw, CU_TENSOR_MAP_L2_PROMOTION_L2_256B,
     CU_TENSOR_MAP_FLOAT_OOB_FILL_NONE);
}
void enc2(EncodeFn fn, CUtensorMap* m, const void* p, uint64_t d0, uint64_t d1, uint64_t s1, uint32_t b0, uint32_t b1,
          CUtensorMapSwizzle sw = CU_TENSOR_MAP_SWIZZLE_128B, CUtensorMapDataType ty = CU_TENSOR_MAP_DATA_TYPE_BFLOAT16) {
  cuuint64_t dims[2] = {d0, d1}, str[1] = {s1}; cuuint32_t box[2] = {b0, b1};
  encode(fn, m, ty, 2, p, dims, str, box, sw);
}
void enc3(EncodeFn fn, CUtensorMap* m, const void* p, uint64_t rows, uint32_t brows, uint32_t b2) {
  cuuint64_t dims[3] = {64, rows, 32}, str[2] = {4096, 128}; cuuint32_t box[3] = {64, brows, b2};
  encode(fn, m, CU_TENSOR_MAP_DATA_TYPE_BFLOAT16, 3, p, dims, str, box, CU_TENSOR_MAP_SWIZZLE_128B);
}

void build_groups(const int* key, int CL, int weight, int* load, uint16_t* mask, uint8_t* lead) {
  for (int c0 = 0; c0 < NCTA; c0 += CL) {
    bool done[16] = {false};
    for (int sz = 1; sz <= CL; sz++)
      for (int r = 0; r < CL; r++) {
        if (done[r]) continue;
        int cnt = 0; uint16_t m = 0;
        for (int u = 0; u < CL; u++) if (key[c0 + u] == key[c0 + r]) { cnt++; m |= (uint16_t)(1u << u); }
        if (cnt != sz) continue;
        int L[2] = {-1, -1};
        for (int k = 0; k < 2; k++) {
          for (int u = 0; u < CL; u++)
            if (((m >> u) & 1) && (k == 0 || u != L[0] || cnt == 1) && (L[k] < 0 || load[c0 + u] < load[c0 + L[k]])) L[k] = u;
          load[c0 + L[k]] += weight;
        }
        for (int u = 0; u < CL; u++) if ((m >> u) & 1) { done[u] = true; mask[c0 + u] = m; lead[c0 + u] = (uint8_t)(L[0] | (L[1] << 4)); }
      }
  }
}

struct Host {
  bool ready;
  const void* key[15];
  Params prm; int cl;
};
Host H;

}

extern "C" void kernel_launch(void* const* d_in, const int* in_sizes, int n_in, void* d_out, int out_size) {
  (void)in_sizes; (void)n_in; (void)out_size;
  bool same = H.ready;
  for (int i = 0; i < 14 && same; i++) same = H.key[i] == d_in[i];
  same = same && H.key[14] == d_out;
  cudaLaunchConfig_t cfg = {};
  cudaLaunchAttribute at[1];
  cfg.gridDim = dim3(NCTA); cfg.blockDim = dim3(512); cfg.dynamicSmemBytes = SMEM_BYTES; cfg.stream = cudaStreamPerThread;
  at[0].id = cudaLaunchAttributeClusterDimension; at[0].val.clusterDim.y = 1; at[0].val.clusterDim.z = 1;
  cfg.attrs = at; cfg.numAttrs = 1;
  if (!same) {
    for (int i = 0; i < 14; i++) H.key[i] = d_in[i];
    H.key[14] = d_out;
    cudaFuncSetAttribute(s5_mixer_kernel, cudaFuncAttributeMaxDynamicSharedMemorySize, SMEM_BYTES);
    cudaFuncSetAttribute(s5_mixer_kernel, cudaFuncAttributeNonPortableClusterSizeAllowed, 1);
    int cl = 1;
    for (int c = 16; c >= 2; c >>= 1) {
      at[0].val.clusterDim.x = c;
      int nc = 0;
      if (cudaOccupancyMaxActiveClusters(&nc, s5_mixer_kernel, &cfg) == cudaSuccess && nc * c >= NCTA) { cl = c; break; }
      (void)cudaGetLastError();
    }
    H.cl = cl;
    void* fp = nullptr; cudaDriverEntryPointQueryResult st;
    cudaGetDriverEntryPoint("cuTensorMapEncodeTiled", &fp, cudaEnableDefault, &st);
    EncodeFn fn = (EncodeFn)fp;
    typedef const __nv_bfloat16* BP;
    Params& P = H.prm;
    P.x = (BP)d_in[0]; P.lre = (BP)d_in[1]; P.lim = (BP)d_in[2]; P.bre = (BP)d_in[3]; P.bim = (BP)d_in[4]; P.cre = (BP)d_in[5]; P.cim = (BP)d_in[6];
    P.logdt = (BP)d_in[7]; P.dskip = (BP)d_in[8]; P.b1 = (BP)d_in[11]; P.b2 = (BP)d_in[13];
    void* scp = nullptr;
    cudaGetSymbolAddress(&scp, g_sc);
    P.sc = (Scratch*)scp;
    const void *hn = P.sc->hn, *hT = P.sc->hT, *G = P.sc->gc;
    Maps& M = P.m;
    {
      cuuint64_t dims[5] = {448, 2, 4, 16, 16}, str[4] = {896, 32 * 896, 2 * 896, 128 * 896}; cuuint32_t box[5] = {64, 2, 4, 16, 1};
      encode(fn, &M.x5, CU_TENSOR_MAP_DATA_TYPE_BFLOAT16, 5, P.x, dims, str, box, CU_TENSOR_MAP_SWIZZLE_128B);
    }
    {
      P.swap = P.bim < P.bre;
      const char *lo = (const char*)(P.swap ? P.bim : P.bre), *hi = (const char*)(P.swap ? P.bre : P.bim);
      cuuint64_t dims[4] = {448, 8, 2, 56}, str[3] = {896, (cuuint64_t)(hi - lo), 8 * 896}; cuuint32_t box[4] = {64, 8, 2, 4};
      encode(fn, &M.bi, CU_TENSOR_MAP_DATA_TYPE_BFLOAT16, 4, lo, dims, str, box, CU_TENSOR_MAP_SWIZZLE_128B);
    }
    enc2(fn, &M.w1, d_in[10], F_, S_, F_ * 2, 64, 64);
    enc2(fn, &M.hn64, hn, 128, 4 * S_, 256, 64, 64); enc2(fn, &M.hn48, hn, 128, 4 * S_, 256, 48, 64);
    enc3(fn, &M.hld, hT, 896, 64, 2); enc3(fn, &M.w2, d_in[12], F_, 64, 2);
    enc3(fn, &M.hst, hT, 896, 32, 1);
    {
      cuuint64_t dims[3] = {112, 4, S_}, str[2] = {(cuuint64_t)S_ * 256, 256}; cuuint32_t box[3] = {112, 4, 4};
      encode(fn, &M.nst, CU_TENSOR_MAP_DATA_TYPE_BFLOAT16, 3, hn, dims, str, box, CU_TENSOR_MAP_SWIZZLE_NONE);
    }
    enc2(fn, &M.gld, G, D_, F_, 896, 64, 64);
    enc2(fn, &M.cld, P.sc->cp, 896, D_, 1792, 64, 64);
    enc2(fn, &M.xt, P.x, D_, S_, 896, 64, 64);
    enc2(fn, &M.gst, G, D_, F_, 896, 112, 16, CU_TENSOR_MAP_SWIZZLE_NONE);
    enc2(fn, &M.ost, d_out, D_, S_, D_ * 4, 32, 32, CU_TENSOR_MAP_SWIZZLE_128B, CU_TENSOR_MAP_DATA_TYPE_FLOAT32);
    int ti[NCTA], tj[NCTA], ft[NCTA], dt[NCTA];
    for (int b = 0; b < NCTA; b++) {
      if (cl == 16) {
        const int c = b / 16, r = b % 16;
        const int full0[6] = {0, 3, 6, 9, 11, 14}, prow[6] = {2, 5, 8, 8, 13, 13}, pcol[6] = {5, 5, 3, 5, 0, 5};
        if (c < 6) {
          if (r < 14) { ti[b] = full0[c] + r / 7; tj[b] = r % 7; }
          else { ti[b] = prow[c]; tj[b] = pcol[c] + r - 14; }
        } else if (r < 10) { ti[b] = r < 5 ? 2 : 5; tj[b] = r % 5; }
        else { ti[b] = r < 13 ? 8 : 13; tj[b] = r < 13 ? r - 10 : r - 11; }
        ft[b] = b / 4; dt[b] = b % 4;
      } else {
        if (b < 64) { ti[b] = 2 * (b / 8) + ((b >> 1) & 1); tj[b] = 2 * ((b >> 2) & 1) + (b & 1); }
        else { ti[b] = (b - 64) / 3; tj[b] = 4 + (b - 64) % 3; }
        ft[b] = 4 * (b / 16) + ((b >> 1) & 3); dt[b] = 2 * ((b >> 3) & 1) + (b & 1);
      }
    }
    uint16_t mAM[NCTA], mAN[NCTA], mBM[NCTA], mBN[NCTA];
    uint8_t lAM[NCTA], lAN[NCTA], lBM[NCTA], lBN[NCTA];
    int loadA[NCTA] = {0}, loadB[NCTA] = {0};
    build_groups(tj, cl, 1, loadA, mAM, lAM);
    build_groups(ti, cl, 2, loadA, mAN, lAN);
    for (int b = 0; b < NCTA; b++) loadB[b] = (lAN[b] & 15) == b % cl || (lAN[b] >> 4) == b % cl ? 4 : 0;
    build_groups(dt, cl, 8, loadB, mBN, lBN);
    build_groups(ft, cl, 1, loadB, mBM, lBM);
    for (int b = 0; b < NCTA; b++) {
      P.tab[b] = make_uint4(ti[b] | (tj[b] << 4) | (ft[b] << 7) | (dt[b] << 12) | (ft[b / cl * cl] << 14) | ((cl == 16 ? 4 : 0) << 19) | (cl << 22), mAM[b] | ((uint32_t)mAN[b] << 16),
                            mBM[b] | ((uint32_t)mBN[b] << 16), lAM[b] | (lAN[b] << 8) | (lBM[b] << 16) | ((uint32_t)lBN[b] << 24));
    }
    H.ready = true;
  }
  at[0].val.clusterDim.x = H.cl;
  cudaLaunchKernelEx(&cfg, s5_mixer_kernel, H.prm);
}
```
